```python
import torch

def _softmax(x, axis=-1):
    return torch.softmax(x, dim=axis)

def _gelu(x):
    return torch.nn.functional.gelu(x, approximate='tanh')

def _silu(x):
    return torch.nn.functional.silu(x)

def _sigmoid(x):
    return torch.sigmoid(x)

def _layernorm(x, axis=-1, eps=1e-05):
    m = x.mean(dim=axis, keepdim=True)
    v = x.var(dim=axis, keepdim=True, unbiased=False)
    return (x - m) / torch.sqrt(v + eps)

def _scatter_add(tgt, idx, src, axis=0):
    return tgt.clone().index_add_(axis, idx, src)

def _segment_sum(src, seg, n):
    out = torch.zeros((n,) + src.shape[1:], dtype=src.dtype)
    return out.index_add_(0, seg, src)

def _pad(x, pw):
    flat = tuple((v for pair in reversed(pw) for v in pair))
    return torch.nn.functional.pad(x, flat)
kernel_name = 'adaLN_cond__mha_block__glu_gated_bilinear__prompt'

def setup_inputs():

    _w = lambda a: (lambda t: t.to(torch.bfloat16) if t.is_floating_point() else t)(torch.as_tensor(a))

    def _A_setup():
        B, S, D, H = (1, 2048, 1024, 32)
        return {'x': _w((lambda *s: torch.randn(*s, dtype=torch.bfloat16) * 0.05)(B, S, D)), 'wqkv': _w((lambda *s: torch.randn(*s, dtype=torch.bfloat16) * 0.05)(D, 3 * D)), 'wo': _w((lambda *s: torch.randn(*s, dtype=torch.bfloat16) * 0.05)(D, D))}
    _A_in = _A_setup()

    def _B_setup():
        B, S, D, F = (1, 2048, 1024, 3584)
        return {'x': _w((lambda *s: torch.randn(*s, dtype=torch.bfloat16) * 0.05)(B, S, D)), 'w_gate': _w((lambda *s: torch.randn(*s, dtype=torch.bfloat16) * 1.6)(D, F) * D ** (-0.5)), 'w_up': _w((lambda *s: torch.randn(*s, dtype=torch.bfloat16) * 1.6)(D, F) * D ** (-0.5)), 'w_down': _w((lambda *s: torch.randn(*s, dtype=torch.bfloat16) * 1.6)(F, D) * F ** (-0.5))}
    _B_in = _B_setup()
    return {'A_x': _A_in['x'], 'A_wqkv': _A_in['wqkv'], 'A_wo': _A_in['wo'], 'B_x': _B_in['x'], 'B_w_gate': _B_in['w_gate'], 'B_w_up': _B_in['w_up'], 'B_w_down': _B_in['w_down'], 'c': _w((lambda *s: torch.randn(*s, dtype=torch.bfloat16) * 0.2)(1, 1024) * 8.0), 'w_mod': _w((lambda *s: torch.randn(*s, dtype=torch.bfloat16) * 0.2)(1024, 6 * 1024) * 1024 ** (-0.5) * 8.0)}

def reference(A_x, A_wqkv, A_wo, B_x, B_w_gate, B_w_up, B_w_down, c, w_mod):

    def _A_ref(x, wqkv, wo):
        B, S, D = x.shape
        H = 32
        Dh = D // H
        qkv = (lambda x, *d: x.permute(*d))((x @ wqkv).reshape(B, S, 3, H, Dh), 2, 0, 3, 1, 4)
        q, k, v = (qkv[0], qkv[1], qkv[2])
        scores = torch.einsum('bhqd,bhkd->bhqk', q, k) * Dh ** (-0.5)
        p = _softmax(scores, axis=-1)
        o = torch.einsum('bhqk,bhkd->bhqd', p, v)
        return (lambda x, *d: x.permute(*d))(o, 0, 2, 1, 3).reshape(B, S, D) @ wo

    def _B_ref(x, w_gate, w_up, w_down):
        g = torch.einsum('bsd,df->bsf', x, w_gate)
        u = torch.einsum('bsd,df->bsf', x, w_up)
        h = g * u
        return torch.einsum('bsf,fd->bsd', h, w_down)
    x = A_x
    mod = (_silu(c) @ w_mod).reshape(c.shape[0], 6, 1, -1)
    sa, ca, ga, sb, cb, gb = (mod[:, 0].clone(), mod[:, 1].clone(), mod[:, 2].clone(), mod[:, 3].clone(), mod[:, 4].clone(), mod[:, 5].clone())
    h = _layernorm(x, axis=-1) * (1 + ca) + sa
    x = x + ga * _A_ref(h, A_wqkv, A_wo)
    h = _layernorm(x, axis=-1) * (1 + cb) + sb
    x = x + gb * _B_ref(h, B_w_gate, B_w_up, B_w_down)
    return x
```

```cpp
#include <cuda_runtime.h>
#include <cuda.h>
#include <cuda_bf16.h>
#include <stdint.h>

typedef __nv_bfloat16 bf16;
constexpr int S_ = 2048, D_ = 1024, H_ = 32, F_ = 3584;

__device__ __align__(16) bf16 g_modh[6 * D_];
__device__ __align__(16) float g_acc[6 * D_];
__device__ __align__(128) unsigned g_cnt[74 * 32];
constexpr int C_H2 = 9 * 32, C_HH = 25 * 32, C_O = 41 * 32, C_MOD = 73 * 32;
__device__ __align__(16) float2 g_stat[S_ * 8];
__device__ __align__(1024) bf16 g_h[S_ * D_];
__device__ __align__(1024) bf16 g_qkv[S_ * 3 * D_];
__device__ __align__(1024) bf16 g_o[S_ * D_];
__device__ __align__(1024) bf16 g_x1[S_ * D_];
__device__ __align__(1024) bf16 g_h2[S_ * D_];
__device__ __align__(1024) bf16 g_hh[S_ * F_];

__device__ __forceinline__ uint32_t smem_u32(const void* p) { return (uint32_t)__cvta_generic_to_shared(p); }
__device__ __forceinline__ void mbar_init(uint32_t bar, int cnt) { asm volatile("mbarrier.init.shared::cta.b64 [%0], %1;" ::"r"(bar), "r"(cnt)); }
__device__ __forceinline__ void mbar_expect_tx(uint32_t bar, uint32_t bytes) { asm volatile("mbarrier.arrive.expect_tx.shared::cta.b64 _, [%0], %1;" ::"r"(bar), "r"(bytes) : "memory"); }
__device__ __forceinline__ void mbar_wait(uint32_t bar, uint32_t parity) {
  asm volatile("{\n.reg .pred p;\n.reg .u32 n;\nmbarrier.try_wait.parity.shared::cta.b64 p, [%0], %1;\n@p bra DONE;\nmov.u32 n, 0;\n"
               "LAB_WAIT:\nmbarrier.try_wait.parity.shared::cta.b64 p, [%0], %1;\n@p bra DONE;\nadd.u32 n, n, 1;\nsetp.lt.u32 p, n, 0x400000;\n@p bra LAB_WAIT;\ntrap;\nDONE:\n}" ::"r"(bar), "r"(parity) : "memory");
}
__device__ __forceinline__ void mbar_wait_long(uint32_t bar, uint32_t parity) {
  asm volatile("{\n.reg .pred p;\n.reg .u32 t0, t1;\nmbarrier.try_wait.parity.shared::cta.b64 p, [%0], %1, 100000;\n@p bra DONE;\nmov.u32 t0, %%globaltimer_hi;\n"
               "LAB_WAIT:\nmbarrier.try_wait.parity.shared::cta.b64 p, [%0], %1, 100000;\n@p bra DONE;\nmov.u32 t1, %%globaltimer_hi;\nsub.u32 t1, t1, t0;\n"
               "setp.lt.u32 p, t1, 2;\n@p bra LAB_WAIT;\ntrap;\nDONE:\n}" ::"r"(bar), "r"(parity) : "memory");
}
__device__ __forceinline__ void mbar_wait_nb(uint32_t bar, uint32_t parity) {
  asm volatile("{\n.reg .pred p;\nLAB_WAIT:\nmbarrier.try_wait.parity.shared::cta.b64 p, [%0], %1;\n@p bra DONE;\nbra LAB_WAIT;\nDONE:\n}" ::"r"(bar), "r"(parity) : "memory");
}
__device__ __forceinline__ unsigned ld_acquire(const unsigned* p) { unsigned v; asm volatile("ld.acquire.gpu.global.u32 %0, [%1];" : "=r"(v) : "l"(p) : "memory"); return v; }
__device__ __forceinline__ void red_release(unsigned* p, unsigned v) { asm volatile("red.release.gpu.global.add.u32 [%0], %1;" ::"l"(p), "r"(v) : "memory"); }
__device__ __forceinline__ void red_relaxed(unsigned* p, unsigned v) { asm volatile("red.relaxed.gpu.global.add.u32 [%0], %1;" ::"l"(p), "r"(v) : "memory"); }
__device__ __forceinline__ void wait_count(const unsigned* p, unsigned target) {
  for (unsigned n = 0; ld_acquire(p) < target; n++) if (n > (1u << 22)) __trap();
}
__device__ __forceinline__ void wait_count_slow(const unsigned* p, unsigned target) {
  for (unsigned n = 0; ld_acquire(p) < target; n++) { __nanosleep(400); if (n > (1u << 20)) __trap(); }
}
__device__ __forceinline__ void mbar_arrive(uint32_t bar) { asm volatile("mbarrier.arrive.shared::cta.b64 _, [%0];" ::"r"(bar) : "memory"); }
__device__ __forceinline__ void tma2d(uint32_t dst, const CUtensorMap* m, int c0, int c1, uint32_t bar) {
  asm volatile("cp.async.bulk.tensor.2d.shared::cluster.global.mbarrier::complete_tx::bytes [%0], [%1, {%3, %4}], [%2];" ::"r"(dst), "l"(m), "r"(bar), "r"(c0), "r"(c1) : "memory");
}
__device__ __forceinline__ void tma2d_store(const CUtensorMap* m, int c0, int c1, uint32_t src) {
  asm volatile("cp.async.bulk.tensor.2d.global.shared::cta.bulk_group [%0, {%1, %2}], [%3];" ::"l"(m), "r"(c0), "r"(c1), "r"(src) : "memory");
}
__device__ __forceinline__ uint32_t elect_one() { uint32_t r; asm volatile("{\n.reg .pred p;\nelect.sync _|p, 0xffffffff;\nselp.u32 %0, 1, 0, p;\n}" : "=r"(r)); return r; }
__device__ __forceinline__ void tma2d_p(uint32_t el, uint32_t dst, const CUtensorMap* m, int c0, int c1, uint32_t bar) {
  asm volatile("{\n.reg .pred p;\nsetp.ne.u32 p, %5, 0;\n@p cp.async.bulk.tensor.2d.shared::cluster.global.mbarrier::complete_tx::bytes [%0], [%1, {%3, %4}], [%2];\n}"
               ::"r"(dst), "l"(m), "r"(bar), "r"(c0), "r"(c1), "r"(el) : "memory");
}
__device__ __forceinline__ void tma2d_mc_p(uint32_t el, uint32_t dst, const CUtensorMap* m, int c0, int c1, uint32_t bar) {
  asm volatile("{\n.reg .pred p;\nsetp.ne.u32 p, %6, 0;\n@p cp.async.bulk.tensor.2d.shared::cluster.global.mbarrier::complete_tx::bytes.multicast::cluster [%0], [%1, {%3, %4}], [%2], %5;\n}"
               ::"r"(dst), "l"(m), "r"(bar), "r"(c0), "r"(c1), "h"((uint16_t)3), "r"(el) : "memory");
}
__device__ __forceinline__ void bulk_ld_p(uint32_t el, uint32_t dst, const void* src, uint32_t bytes, uint32_t bar) {
  asm volatile("{\n.reg .pred p;\nsetp.ne.u32 p, %4, 0;\n@p cp.async.bulk.shared::cluster.global.mbarrier::complete_tx::bytes [%0], [%1], %2, [%3];\n}"
               ::"r"(dst), "l"(src), "r"(bytes), "r"(bar), "r"(el) : "memory");
}
__device__ __forceinline__ void expect_tx_p(uint32_t el, uint32_t bar, uint32_t bytes) {
  asm volatile("{\n.reg .pred p;\nsetp.ne.u32 p, %2, 0;\n@p mbarrier.arrive.expect_tx.shared::cta.b64 _, [%0], %1;\n}" ::"r"(bar), "r"(bytes), "r"(el) : "memory");
}
__device__ __forceinline__ void arrive_p(uint32_t el, uint32_t bar) {
  asm volatile("{\n.reg .pred p;\nsetp.ne.u32 p, %1, 0;\n@p mbarrier.arrive.shared::cta.b64 _, [%0];\n}" ::"r"(bar), "r"(el) : "memory");
}
__device__ __forceinline__ void prefetch_tmap(const CUtensorMap* m) { asm volatile("prefetch.tensormap [%0];" ::"l"(m) : "memory"); }
__device__ __forceinline__ void wg_fence() { asm volatile("wgmma.fence.sync.aligned;" ::: "memory"); }
__device__ __forceinline__ void wg_commit() { asm volatile("wgmma.commit_group.sync.aligned;" ::: "memory"); }
template <int N> __device__ __forceinline__ void wg_wait() { asm volatile("wgmma.wait_group.sync.aligned %0;" ::"n"(N) : "memory"); }
template <int R> __device__ __forceinline__ void reg_alloc() { asm volatile("setmaxnreg.inc.sync.aligned.u32 %0;" ::"n"(R)); }
template <int R> __device__ __forceinline__ void reg_dealloc() { asm volatile("setmaxnreg.dec.sync.aligned.u32 %0;" ::"n"(R)); }
__device__ __forceinline__ uint64_t make_desc(uint32_t addr, uint32_t lbo, uint32_t sbo, uint32_t mode) {
  return (uint64_t)((addr & 0x3FFFF) >> 4) | ((uint64_t)((lbo & 0x3FFFF) >> 4) << 16) | ((uint64_t)((sbo & 0x3FFFF) >> 4) << 32) | ((uint64_t)mode << 62);
}
__device__ __forceinline__ uint32_t pack_bf16(float lo, float hi) { uint32_t r; asm("cvt.rn.bf16x2.f32 %0, %1, %2;" : "=r"(r) : "f"(hi), "f"(lo)); return r; }
__device__ __forceinline__ uint32_t hmul2bf(uint32_t a, uint32_t b) { uint32_t d; asm("mul.rn.bf16x2 %0,%1,%2;" : "=r"(d) : "r"(a), "r"(b)); return d; }
__device__ __forceinline__ uint32_t hadd2bf(uint32_t a, uint32_t b) { uint32_t d; asm("add.rn.bf16x2 %0,%1,%2;" : "=r"(d) : "r"(a), "r"(b)); return d; }
__device__ __forceinline__ float bf_lo(uint32_t v) { return __uint_as_float(v << 16); }
__device__ __forceinline__ float bf_hi(uint32_t v) { return __uint_as_float(v & 0xffff0000u); }
__device__ __forceinline__ float bf_round(float x) { return __bfloat162float(__float2bfloat16_rn(x)); }
__device__ __forceinline__ float ex2f(float x) { float y; asm("ex2.approx.ftz.f32 %0, %1;" : "=f"(y) : "f"(x)); return y; }
template <int N> __device__ __forceinline__ void fence_regs(float (&d)[N]) {
#pragma unroll
  for (int i = 0; i < N; i++) asm volatile("" : "+f"(d[i])::"memory");
}
__device__ __forceinline__ void stsm4(uint32_t addr, uint32_t r0, uint32_t r1, uint32_t r2, uint32_t r3) {
  asm volatile("stmatrix.sync.aligned.m8n8.x4.shared.b16 [%0],{%1,%2,%3,%4};" ::"r"(addr), "r"(r0), "r"(r1), "r"(r2), "r"(r3) : "memory");
}
__device__ __forceinline__ void ldsm4(uint32_t (&r)[4], uint32_t addr) {
  asm volatile("ldmatrix.sync.aligned.m8n8.x4.shared.b16 {%0,%1,%2,%3},[%4];" : "=r"(r[0]), "=r"(r[1]), "=r"(r[2]), "=r"(r[3]) : "r"(addr) : "memory");
}
__device__ __forceinline__ void pdl_wait() { asm volatile("griddepcontrol.wait;" ::: "memory"); }
__device__ __forceinline__ void pdl_launch() { asm volatile("griddepcontrol.launch_dependents;" ::: "memory"); }
__device__ __forceinline__ void named_bar(int id, int n) { asm volatile("bar.sync %0, %1;" ::"r"(id), "r"(n) : "memory"); }
__device__ __forceinline__ void bar_arrive(int id, int n) { asm volatile("bar.arrive %0, %1;" ::"r"(id), "r"(n) : "memory"); }
__device__ __forceinline__ void cluster_arrive() { asm volatile("barrier.cluster.arrive.relaxed.aligned;" ::: "memory"); }
__device__ __forceinline__ void cluster_wait() { asm volatile("barrier.cluster.wait.aligned;" ::: "memory"); }
__device__ __forceinline__ void arrive_remote(uint32_t bar, uint32_t cta) {
  asm volatile("{\n.reg .b32 ra;\nmapa.shared::cluster.u32 ra, %0, %1;\nmbarrier.arrive.shared::cluster.b64 _, [ra];\n}" ::"r"(bar), "r"(cta) : "memory");
}
__device__ __forceinline__ void arrive8_remote(uint32_t bar, uint32_t cta) {
  asm volatile("{\n.reg .b32 ra;\nmapa.shared::cluster.u32 ra, %0, %1;\nmbarrier.arrive.shared::cluster.b64 _, [ra], 8;\n}" ::"r"(bar), "r"(cta) : "memory");
}
__device__ __forceinline__ void fence_async() { asm volatile("fence.proxy.async.shared::cta;" ::: "memory"); }

__device__ __forceinline__ void wgmma_rs_n64_tb0(float (&d)[32], uint32_t a0, uint32_t a1, uint32_t a2, uint32_t a3, uint64_t db, int sd) {
  asm volatile("{\n.reg .pred p;\nsetp.ne.b32 p, %37, 0;\n"
    "wgmma.mma_async.sync.aligned.m64n64k16.f32.bf16.bf16 {%0, %1, %2, %3, %4, %5, %6, %7, %8, %9, %10, %11, %12, %13, %14, %15, %16, %17, %18, %19, %20, %21, %22, %23, %24, %25, %26, %27, %28, %29, %30, %31}, {%32, %33, %34, %35}, %36, p, 1, 1, 0;\n}\n"
    : "+f"(d[0]), "+f"(d[1]), "+f"(d[2]), "+f"(d[3]), "+f"(d[4]), "+f"(d[5]), "+f"(d[6]), "+f"(d[7]), "+f"(d[8]), "+f"(d[9]), "+f"(d[10]), "+f"(d[11]), "+f"(d[12]), "+f"(d[13]), "+f"(d[14]), "+f"(d[15]), "+f"(d[16]), "+f"(d[17]), "+f"(d[18]), "+f"(d[19]), "+f"(d[20]), "+f"(d[21]), "+f"(d[22]), "+f"(d[23]), "+f"(d[24]), "+f"(d[25]), "+f"(d[26]), "+f"(d[27]), "+f"(d[28]), "+f"(d[29]), "+f"(d[30]), "+f"(d[31])
    : "r"(a0), "r"(a1), "r"(a2), "r"(a3), "l"(db), "r"(sd));
}

__device__ __forceinline__ void wgmma_rs0_n64_tb0(float (&d)[32], uint32_t a0, uint32_t a1, uint32_t a2, uint32_t a3, uint64_t db) {
  asm volatile(
    "wgmma.mma_async.sync.aligned.m64n64k16.f32.bf16.bf16 {%0, %1, %2, %3, %4, %5, %6, %7, %8, %9, %10, %11, %12, %13, %14, %15, %16, %17, %18, %19, %20, %21, %22, %23, %24, %25, %26, %27, %28, %29, %30, %31}, {%32, %33, %34, %35}, %36, 0, 1, 1, 0;\n"
    : "=f"(d[0]), "=f"(d[1]), "=f"(d[2]), "=f"(d[3]), "=f"(d[4]), "=f"(d[5]), "=f"(d[6]), "=f"(d[7]), "=f"(d[8]), "=f"(d[9]), "=f"(d[10]), "=f"(d[11]), "=f"(d[12]), "=f"(d[13]), "=f"(d[14]), "=f"(d[15]), "=f"(d[16]), "=f"(d[17]), "=f"(d[18]), "=f"(d[19]), "=f"(d[20]), "=f"(d[21]), "=f"(d[22]), "=f"(d[23]), "=f"(d[24]), "=f"(d[25]), "=f"(d[26]), "=f"(d[27]), "=f"(d[28]), "=f"(d[29]), "=f"(d[30]), "=f"(d[31])
    : "r"(a0), "r"(a1), "r"(a2), "r"(a3), "l"(db));
}

__device__ __forceinline__ void wgmma_rs_n40_tb1(float (&d)[20], uint32_t a0, uint32_t a1, uint32_t a2, uint32_t a3, uint64_t db, int sd) {
  asm volatile("{\n.reg .pred p;\nsetp.ne.b32 p, %25, 0;\n"
    "wgmma.mma_async.sync.aligned.m64n40k16.f32.bf16.bf16 {%0, %1, %2, %3, %4, %5, %6, %7, %8, %9, %10, %11, %12, %13, %14, %15, %16, %17, %18, %19}, {%20, %21, %22, %23}, %24, p, 1, 1, 1;\n}\n"
    : "+f"(d[0]), "+f"(d[1]), "+f"(d[2]), "+f"(d[3]), "+f"(d[4]), "+f"(d[5]), "+f"(d[6]), "+f"(d[7]), "+f"(d[8]), "+f"(d[9]), "+f"(d[10]), "+f"(d[11]), "+f"(d[12]), "+f"(d[13]), "+f"(d[14]), "+f"(d[15]), "+f"(d[16]), "+f"(d[17]), "+f"(d[18]), "+f"(d[19])
    : "r"(a0), "r"(a1), "r"(a2), "r"(a3), "l"(db), "r"(sd));
}

__device__ __forceinline__ void wgmma_ss_n128_tb1(float (&d)[64], uint64_t da, uint64_t db, int sd) {
  asm volatile("{\n.reg .pred p;\nsetp.ne.b32 p, %66, 0;\n"
    "wgmma.mma_async.sync.aligned.m64n128k16.f32.bf16.bf16 {%0, %1, %2, %3, %4, %5, %6, %7, %8, %9, %10, %11, %12, %13, %14, %15, %16, %17, %18, %19, %20, %21, %22, %23, %24, %25, %26, %27, %28, %29, %30, %31, %32, %33, %34, %35, %36, %37, %38, %39, %40, %41, %42, %43, %44, %45, %46, %47, %48, %49, %50, %51, %52, %53, %54, %55, %56, %57, %58, %59, %60, %61, %62, %63}, %64, %65, p, 1, 1, 0, 1;\n}\n"
    : "+f"(d[0]), "+f"(d[1]), "+f"(d[2]), "+f"(d[3]), "+f"(d[4]), "+f"(d[5]), "+f"(d[6]), "+f"(d[7]), "+f"(d[8]), "+f"(d[9]), "+f"(d[10]), "+f"(d[11]), "+f"(d[12]), "+f"(d[13]), "+f"(d[14]), "+f"(d[15]), "+f"(d[16]), "+f"(d[17]), "+f"(d[18]), "+f"(d[19]), "+f"(d[20]), "+f"(d[21]), "+f"(d[22]), "+f"(d[23]), "+f"(d[24]), "+f"(d[25]), "+f"(d[26]), "+f"(d[27]), "+f"(d[28]), "+f"(d[29]), "+f"(d[30]), "+f"(d[31]), "+f"(d[32]), "+f"(d[33]), "+f"(d[34]), "+f"(d[35]), "+f"(d[36]), "+f"(d[37]), "+f"(d[38]), "+f"(d[39]), "+f"(d[40]), "+f"(d[41]), "+f"(d[42]), "+f"(d[43]), "+f"(d[44]), "+f"(d[45]), "+f"(d[46]), "+f"(d[47]), "+f"(d[48]), "+f"(d[49]), "+f"(d[50]), "+f"(d[51]), "+f"(d[52]), "+f"(d[53]), "+f"(d[54]), "+f"(d[55]), "+f"(d[56]), "+f"(d[57]), "+f"(d[58]), "+f"(d[59]), "+f"(d[60]), "+f"(d[61]), "+f"(d[62]), "+f"(d[63])
    : "l"(da), "l"(db), "r"(sd));
}

__device__ __forceinline__ void wgmma_ss_n192_tb1(float (&d)[96], uint64_t da, uint64_t db, int sd) {
  asm volatile("{\n.reg .pred p;\nsetp.ne.b32 p, %98, 0;\n"
    "wgmma.mma_async.sync.aligned.m64n192k16.f32.bf16.bf16 {%0, %1, %2, %3, %4, %5, %6, %7, %8, %9, %10, %11, %12, %13, %14, %15, %16, %17, %18, %19, %20, %21, %22, %23, %24, %25, %26, %27, %28, %29, %30, %31, %32, %33, %34, %35, %36, %37, %38, %39, %40, %41, %42, %43, %44, %45, %46, %47, %48, %49, %50, %51, %52, %53, %54, %55, %56, %57, %58, %59, %60, %61, %62, %63, %64, %65, %66, %67, %68, %69, %70, %71, %72, %73, %74, %75, %76, %77, %78, %79, %80, %81, %82, %83, %84, %85, %86, %87, %88, %89, %90, %91, %92, %93, %94, %95}, %96, %97, p, 1, 1, 0, 1;\n}\n"
    : "+f"(d[0]), "+f"(d[1]), "+f"(d[2]), "+f"(d[3]), "+f"(d[4]), "+f"(d[5]), "+f"(d[6]), "+f"(d[7]), "+f"(d[8]), "+f"(d[9]), "+f"(d[10]), "+f"(d[11]), "+f"(d[12]), "+f"(d[13]), "+f"(d[14]), "+f"(d[15]), "+f"(d[16]), "+f"(d[17]), "+f"(d[18]), "+f"(d[19]), "+f"(d[20]), "+f"(d[21]), "+f"(d[22]), "+f"(d[23]), "+f"(d[24]), "+f"(d[25]), "+f"(d[26]), "+f"(d[27]), "+f"(d[28]), "+f"(d[29]), "+f"(d[30]), "+f"(d[31]), "+f"(d[32]), "+f"(d[33]), "+f"(d[34]), "+f"(d[35]), "+f"(d[36]), "+f"(d[37]), "+f"(d[38]), "+f"(d[39]), "+f"(d[40]), "+f"(d[41]), "+f"(d[42]), "+f"(d[43]), "+f"(d[44]), "+f"(d[45]), "+f"(d[46]), "+f"(d[47]), "+f"(d[48]), "+f"(d[49]), "+f"(d[50]), "+f"(d[51]), "+f"(d[52]), "+f"(d[53]), "+f"(d[54]), "+f"(d[55]), "+f"(d[56]), "+f"(d[57]), "+f"(d[58]), "+f"(d[59]), "+f"(d[60]), "+f"(d[61]), "+f"(d[62]), "+f"(d[63]), "+f"(d[64]), "+f"(d[65]), "+f"(d[66]), "+f"(d[67]), "+f"(d[68]), "+f"(d[69]), "+f"(d[70]), "+f"(d[71]), "+f"(d[72]), "+f"(d[73]), "+f"(d[74]), "+f"(d[75]), "+f"(d[76]), "+f"(d[77]), "+f"(d[78]), "+f"(d[79]), "+f"(d[80]), "+f"(d[81]), "+f"(d[82]), "+f"(d[83]), "+f"(d[84]), "+f"(d[85]), "+f"(d[86]), "+f"(d[87]), "+f"(d[88]), "+f"(d[89]), "+f"(d[90]), "+f"(d[91]), "+f"(d[92]), "+f"(d[93]), "+f"(d[94]), "+f"(d[95])
    : "l"(da), "l"(db), "r"(sd));
}

template <int N> __device__ __forceinline__ void wgmma_ss(float (&d)[N / 2], uint64_t da, uint64_t db, int sd) {
  if constexpr (N == 128) wgmma_ss_n128_tb1(d, da, db, sd);
  else wgmma_ss_n192_tb1(d, da, db, sd);
}

constexpr float QSCALE = 5.421010862427522e-20f;
__device__ __forceinline__ float silu_bf(const bf16* c, int k) { const float v = __bfloat162float(c[k]); return bf_round(v / (1.f + __expf(-v))); }
__device__ __forceinline__ void fma8(float (&a)[8], float s, const uint4& v) {
  a[0] = fmaf(s, bf_lo(v.x), a[0]); a[1] = fmaf(s, bf_hi(v.x), a[1]); a[2] = fmaf(s, bf_lo(v.y), a[2]); a[3] = fmaf(s, bf_hi(v.y), a[3]);
  a[4] = fmaf(s, bf_lo(v.z), a[4]); a[5] = fmaf(s, bf_hi(v.z), a[5]); a[6] = fmaf(s, bf_lo(v.w), a[6]); a[7] = fmaf(s, bf_hi(v.w), a[7]);
}
__device__ __forceinline__ void red_add4(float* p, float a, float b, float c, float d) {
  asm volatile("red.global.add.v4.f32 [%0], {%1,%2,%3,%4};" ::"l"(p), "f"(a), "f"(b), "f"(c), "f"(d) : "memory");
}
__device__ __forceinline__ uint4 ldg_stream(const void* p) {
  uint4 v; asm volatile("ld.global.nc.L1::no_allocate.v4.u32 {%0,%1,%2,%3}, [%4];" : "=r"(v.x), "=r"(v.y), "=r"(v.z), "=r"(v.w) : "l"(p) : "memory"); return v;
}

__global__ void __launch_bounds__(384, 1) k_qkv(const __grid_constant__ CUtensorMap tmA, const __grid_constant__ CUtensorMap tmB,
                                                const bf16* __restrict__ x, const bf16* __restrict__ c, const bf16* __restrict__ wm) {
  constexpr int BM = 256, BN = 192, STAGES = 4, KT = 16, ABYTES = BM * 128, SBYTES = (BM + BN) * 128;
  extern __shared__ uint8_t smem_raw[];
  __shared__ uint64_t full[STAGES], empty[STAGES], scrfree;
  const uint32_t sbase = (smem_u32(smem_raw) + 1023) & ~1023u;
  const int wg = __shfl_sync(~0u, threadIdx.x / 128, 0), tid = threadIdx.x % 128, warp = __shfl_sync(~0u, tid / 32, 0), lane = tid % 32;
  const int bid = blockIdx.x, rk = bid & 1, mi = (bid >> 1) & 7, ni = (bid >> 4) * 2 + rk;
  if (wg == 0) {
    if (tid == 0) {
      for (int s = 0; s < STAGES; s++) { mbar_init(smem_u32(&full[s]), 1); mbar_init(smem_u32(&empty[s]), 16); }
      mbar_init(smem_u32(&scrfree), 2);
      asm volatile("fence.mbarrier_init.release.cluster;" ::: "memory");
      fence_async();
    }
    __syncthreads();
    cluster_arrive();
    reg_dealloc<40>();
    pdl_launch();
    if (warp == 0) {
      const uint32_t el = elect_one();
      if (lane == 0) prefetch_tmap(&tmB);
      named_bar(9, 288);
#pragma unroll 1
      for (int k = 0; k < STAGES; k++) {
        expect_tx_p(el, smem_u32(&full[k]), SBYTES);
#pragma unroll
        for (int cc = 0; cc < 3; cc++) tma2d_p(el, sbase + k * SBYTES + ABYTES + cc * 8192, &tmB, ni * BN + cc * 64, k * 64, smem_u32(&full[k]));
      }
      if (lane == 0) prefetch_tmap(&tmA);
      cluster_wait();
      wait_count(&g_cnt[(1 + mi) * 32], 16);
      __syncwarp();
      mbar_wait(smem_u32(&scrfree), 0);
      fence_async();
      int s = 0, ph = 1;
#pragma unroll 1
      for (int k = 0; k < KT; k++) {
        const uint32_t fb = smem_u32(&full[s]);
        if (k >= STAGES) {
          mbar_wait(smem_u32(&empty[s]), ph);
          expect_tx_p(el, fb, SBYTES);
#pragma unroll
          for (int cc = 0; cc < 3; cc++) tma2d_p(el, sbase + s * SBYTES + ABYTES + cc * 8192, &tmB, ni * BN + cc * 64, k * 64, fb);
        }
        tma2d_mc_p(el, sbase + s * SBYTES + rk * (ABYTES / 2), &tmA, k * 64, mi * BM + rk * 128, fb);
        if (++s == STAGES) { s = 0; ph ^= 1; }
      }
      cluster_arrive();
    } else {
      cluster_wait();
      cluster_arrive();
      if (warp == 1) {
        named_bar(4, 96);
        if (lane == 0) { red_release(&g_cnt[0], 1); }
        if (bid < 33 && lane == 0) g_cnt[(41 + bid) * 32] = 0;
        __syncwarp();
      }
      wait_count_slow(&g_cnt[(1 + mi) * 32], 16);
      const int col = 2 * D_ + (bid & 15) * 256 + lane * 8, r0 = (bid >> 4) * 128;
      float a[8] = {0, 0, 0, 0, 0, 0, 0, 0};
      for (int r = warp - 1; r < 128; r += 12) {
        uint4 v[4];
#pragma unroll
        for (int i = 0; i < 4; i++) if (r + 3 * i < 128) v[i] = ldg_stream(wm + (size_t)(r0 + r + 3 * i) * (6 * D_) + col);
#pragma unroll
        for (int i = 0; i < 4; i++) if (r + 3 * i < 128) fma8(a, silu_bf(c, r0 + r + 3 * i), v[i]);
      }
      red_add4(g_acc + col, a[0], a[1], a[2], a[3]);
      red_add4(g_acc + col + 4, a[4], a[5], a[6], a[7]);
    }
    cluster_wait();
  } else {
    const int w = wg - 1, cw = w * 4 + warp, ct = threadIdx.x - 128;
    uint4 wv[8], xv[2][4];
    {
      const bf16* wp = wm + (size_t)((bid >> 3) * 64 + cw * 8) * (6 * D_) + (bid & 7) * 256 + lane * 8;
#pragma unroll
      for (int i = 0; i < 8; i++) wv[i] = ldg_stream(wp + (size_t)i * (6 * D_));
    }
    const float sv = silu_bf(c, (bid >> 3) * 64 + cw * 8 + (lane & 7));
    __syncthreads();
    cluster_arrive();
    reg_alloc<232>();
    float* scr = (float*)(smem_raw + (sbase - smem_u32(smem_raw)));
    {
      float a[8] = {0, 0, 0, 0, 0, 0, 0, 0};
#pragma unroll
      for (int i = 0; i < 8; i++) fma8(a, __shfl_sync(~0u, sv, i), wv[i]);
      *(float4*)(scr + cw * 256 + lane * 8) = make_float4(a[0], a[1], a[2], a[3]);
      *(float4*)(scr + cw * 256 + lane * 8 + 4) = make_float4(a[4], a[5], a[6], a[7]);
      named_bar(1, 256);
#pragma unroll
      for (int r = 0; r < 2; r++)
#pragma unroll
        for (int i = 0; i < 4; i++) xv[r][i] = ldg_stream(x + (size_t)(bid * 16 + cw * 2 + r) * D_ + i * 256 + lane * 8);
      if (ct < 64) {
        float4 t = *(float4*)(scr + ct * 4);
#pragma unroll
        for (int k = 1; k < 8; k++) { const float4 u = *(float4*)(scr + k * 256 + ct * 4); t.x += u.x; t.y += u.y; t.z += u.z; t.w += u.w; }
        red_add4(g_acc + (bid & 7) * 256 + ct * 4, t.x, t.y, t.z, t.w);
        bar_arrive(4, 96);
      }
    }
    uint32_t nv[2][16];
#pragma unroll
    for (int r = 0; r < 2; r++) {
      float f[32];
#pragma unroll
      for (int i = 0; i < 4; i++) {
        f[8 * i + 0] = bf_lo(xv[r][i].x); f[8 * i + 1] = bf_hi(xv[r][i].x); f[8 * i + 2] = bf_lo(xv[r][i].y); f[8 * i + 3] = bf_hi(xv[r][i].y);
        f[8 * i + 4] = bf_lo(xv[r][i].z); f[8 * i + 5] = bf_hi(xv[r][i].z); f[8 * i + 6] = bf_lo(xv[r][i].w); f[8 * i + 7] = bf_hi(xv[r][i].w);
      }
      float sum = 0;
#pragma unroll
      for (int i = 0; i < 32; i++) sum += f[i];
#pragma unroll
      for (int o = 16; o; o >>= 1) sum += __shfl_xor_sync(~0u, sum, o);
      const float mean = sum * (1.f / D_);
      float q = 0;
#pragma unroll
      for (int i = 0; i < 32; i++) { const float d = f[i] - mean; q = fmaf(d, d, q); }
#pragma unroll
      for (int o = 16; o; o >>= 1) q += __shfl_xor_sync(~0u, q, o);
      const float mb = bf_round(mean), rs = 1.f / bf_round(sqrtf(bf_round(bf_round(q * (1.f / D_)) + 1e-5f)));
#pragma unroll
      for (int i = 0; i < 16; i++) {
        const uint32_t d = pack_bf16(f[2 * i] - mb, f[2 * i + 1] - mb);
        nv[r][i] = pack_bf16(bf_lo(d) * rs, bf_hi(d) * rs);
      }
    }
    if (ct == 0) { wait_count(&g_cnt[0], 128); }
    named_bar(1, 256);
    {
      const float4 t0 = __ldcg((const float4*)(g_acc + ct * 8)), t1 = __ldcg((const float4*)(g_acc + ct * 8 + 4));
      const float add = ct >= 128 ? 1.f : 0.f;
      *(uint4*)(scr + 2048 + ct * 4) = make_uint4(pack_bf16(bf_round(t0.x) + add, bf_round(t0.y) + add), pack_bf16(bf_round(t0.z) + add, bf_round(t0.w) + add),
                                                  pack_bf16(bf_round(t1.x) + add, bf_round(t1.y) + add), pack_bf16(bf_round(t1.z) + add, bf_round(t1.w) + add));
    }
    named_bar(1, 256);
    bar_arrive(9, 288);
#pragma unroll
    for (int i = 0; i < 4; i++) {
      const uint4 b = *(const uint4*)(scr + 2048 + i * 128 + lane * 4), a = *(const uint4*)(scr + 2560 + i * 128 + lane * 4);
#pragma unroll
      for (int r = 0; r < 2; r++)
        *(uint4*)((uint8_t*)scr + SBYTES + (cw * 2 + r) * 2048 + i * 512 + lane * 16) =
            make_uint4(hadd2bf(hmul2bf(nv[r][4 * i], a.x), b.x), hadd2bf(hmul2bf(nv[r][4 * i + 1], a.y), b.y),
                       hadd2bf(hmul2bf(nv[r][4 * i + 2], a.z), b.z), hadd2bf(hmul2bf(nv[r][4 * i + 3], a.w), b.w));
    }
    fence_async();
    named_bar(1, 256);
    if (ct == 0) {
      asm volatile("cp.async.bulk.global.shared::cta.bulk_group [%0], [%1], %2;" ::"l"(g_h + (size_t)bid * 16 * D_), "r"(sbase + SBYTES), "r"(32768) : "memory");
      asm volatile("cp.async.bulk.commit_group;" ::: "memory");
      asm volatile("cp.async.bulk.wait_group 0;" ::: "memory");
      red_relaxed(&g_cnt[(1 + (bid >> 4)) * 32], 1);
    }
    __syncwarp();
    cluster_wait();
    if (ct < 2) arrive_remote(smem_u32(&scrfree), ct);
    int s = 0, ph = 0, sp = 0;
    const uint64_t da0 = make_desc(sbase + w * 128 * 128, 16, 1024, 1), db0 = make_desc(sbase + ABYTES, 8192, 1024, 1);
    float acc[2][BN / 2];
    if (w == 1) named_bar(8, 256);
#pragma unroll 1
    for (int k = 0; k < KT; k++) {
      mbar_wait(smem_u32(&full[s]), ph);
      wg_fence();
      const uint64_t da = da0 + s * (SBYTES >> 4), db = db0 + s * (SBYTES >> 4);
#pragma unroll
      for (int kk = 0; kk < 4; kk++) {
#pragma unroll
        for (int m = 0; m < 2; m++) wgmma_ss<BN>(acc[m], da + m * 512 + kk * 2, db + kk * 128, (k | kk) != 0);
      }
      wg_commit();
      if (w == 0 && k == 1) bar_arrive(8, 256);
      if (k > 0) { wg_wait<1>(); if (lane < 2) arrive_remote(smem_u32(&empty[sp]), lane); }
      sp = s;
      if (++s == STAGES) { s = 0; ph ^= 1; }
    }
    wg_wait<0>();
    cluster_arrive();
    fence_regs(acc[0]); fence_regs(acc[1]);
    mbar_wait(smem_u32(&empty[w]), 1);
    const int srow = warp * 16 + (lane & 15);
    const uint32_t sa = sbase + w * SBYTES + srow * 64, sx = (srow >> 1) & 3;
#pragma unroll
    for (int m = 0; m < 2; m++) {
#pragma unroll
      for (int j = 0; j < BN / 16; j++) {
        const float sc = (ni * BN + j * 16 < D_) ? QSCALE : 1.f;
        stsm4(sa + m * 24576 + (j >> 1) * 4096 + ((((j & 1) * 2 + (lane >> 4)) ^ sx) << 4),
              pack_bf16(acc[m][8 * j] * sc, acc[m][8 * j + 1] * sc), pack_bf16(acc[m][8 * j + 2] * sc, acc[m][8 * j + 3] * sc),
              pack_bf16(acc[m][8 * j + 4] * sc, acc[m][8 * j + 5] * sc), pack_bf16(acc[m][8 * j + 6] * sc, acc[m][8 * j + 7] * sc));
      }
      fence_async();
      named_bar(2 + w, 128);
      if (tid < 6) {
        asm volatile("cp.async.bulk.global.shared::cta.bulk_group [%0], [%1], %2;"
                     ::"l"(g_qkv + ((size_t)(ni * 6 + tid) * S_ + mi * BM + w * 128 + m * 64) * 32), "r"(sbase + w * SBYTES + m * 24576 + tid * 4096), "r"(4096) : "memory");
        asm volatile("cp.async.bulk.commit_group;" ::: "memory");
      }
    }
    if (tid < 6) { asm volatile("cp.async.bulk.wait_group.read 0;" ::: "memory"); }
    __syncwarp();
    cluster_wait();
  }
}

constexpr float SCL2 = 0.17677669529663687f * 1.4426950408889634f;
constexpr float SCQ = SCL2 * 18446744073709551616.f;
constexpr float SCD = SCL2 * 3.308722450212111e-24f;
constexpr float OFFS = 40.f;

__device__ __forceinline__ uint32_t hfma2bf(uint32_t a, uint32_t b, uint32_t c) { uint32_t d; asm("fma.rn.bf16x2 %0,%1,%2,%3;" : "=r"(d) : "r"(a), "r"(b), "r"(c)); return d; }
__device__ __forceinline__ uint32_t exp2_pair_a(float s0, float s1, float bden) {
  float t0, t1;
  asm("fma.rn.f32 %0,%1,%2,%3;" : "=f"(t0) : "f"(s0), "f"(SCD), "f"(bden));
  asm("fma.rn.f32 %0,%1,%2,%3;" : "=f"(t1) : "f"(s1), "f"(SCD), "f"(bden));
  uint32_t w;
  asm("cvt.pack.sat.s16.s32 %0,%1,%2;" : "=r"(w) : "r"(__float_as_uint(t1)), "r"(__float_as_uint(t0)));
  return w;
}
__device__ __forceinline__ uint32_t exp2_pair_b(uint32_t w, uint32_t c_one, uint32_t c_s) {
  uint32_t mf;
  asm("lop3.b32 %0,%1,0x007F007F,%2,0xEA;" : "=r"(mf) : "r"(w), "r"(c_one));
  const uint32_t u = hfma2bf(mf, c_s, 0xBF36BF36u);
  const uint32_t h = hfma2bf(u, u, 0xBD6DBD6Du);
  return hfma2bf(w, h, w);
}
#define PKM 0x5557
__device__ __forceinline__ void exp_a(float (&sc)[32], float b0, float b1, float M0, float M1) {
#pragma unroll
  for (int q = 0; q < 16; q++) {
    if ((PKM >> q) & 1) sc[2 * q] = __uint_as_float(exp2_pair_a(sc[2 * q], sc[2 * q + 1], (q & 1) ? b1 : b0));
    else { sc[2 * q] = ex2f(fmaf(sc[2 * q], SCQ, -((q & 1) ? M1 : M0))); sc[2 * q + 1] = ex2f(fmaf(sc[2 * q + 1], SCQ, -((q & 1) ? M1 : M0))); }
  }
}
__device__ __forceinline__ void exp_b(float (&sc)[32], uint32_t (&p)[16], uint32_t c_one, uint32_t c_s) {
#pragma unroll
  for (int q = 0; q < 16; q++) p[q] = ((PKM >> q) & 1) ? exp2_pair_b(__float_as_uint(sc[2 * q]), c_one, c_s) : pack_bf16(sc[2 * q], sc[2 * q + 1]);
}
__device__ __forceinline__ void qk64(float (&sc)[32], const uint32_t (&q)[8], uint64_t dk) {
  wgmma_rs0_n64_tb0(sc, q[0], q[1], q[2], q[3], dk);
  wgmma_rs_n64_tb0(sc, q[4], q[5], q[6], q[7], dk + 2, 1);
}
__device__ __forceinline__ float den_bits(float M) {
  const int v = (127 - (int)M) * 128;
  return __uint_as_float(v >= 0 ? (uint32_t)v : (0x80000000u | (uint32_t)(-v)));
}
__device__ __forceinline__ float qkv_at(int mat, int h, int row, int d) {
  return __bfloat162float(g_qkv[((size_t)(mat * 32 + h) * S_ + row) * 32 + ((((d >> 3) ^ ((row >> 1) & 3)) << 3) | (d & 7))]);
}
__device__ __forceinline__ float row_score(int h, int k, float qd) {
  float s = 0;
#pragma unroll 1
  for (int d = 0; d < 32; d++) s = fmaf(__shfl_sync(~0u, qd, d), qkv_at(1, h, k, d), s);
  return s;
}
__device__ __forceinline__ void attn_row_exact(int h, int row, int lane, uint32_t dst_row) {
  const float qd = qkv_at(0, h, row, lane) * SCQ;
  float mx = -INFINITY;
#pragma unroll 1
  for (int k = lane; k < S_; k += 32) mx = fmaxf(mx, row_score(h, k, qd));
#pragma unroll 1
  for (int o = 16; o; o >>= 1) mx = fmaxf(mx, __shfl_xor_sync(~0u, mx, o));
  float acc = 0, l = 0;
#pragma unroll 1
  for (int k0 = 0; k0 < S_; k0 += 32) {
    const float p = exp2f(row_score(h, k0 + lane, qd) - mx);
    l += p;
#pragma unroll 1
    for (int k = 0; k < 32; k++) acc = fmaf(__shfl_sync(~0u, p, k), qkv_at(2, h, k0 + k, lane), acc);
  }
#pragma unroll 1
  for (int o = 16; o; o >>= 1) l += __shfl_xor_sync(~0u, l, o);
  const unsigned short hv = __bfloat16_as_ushort(__float2bfloat16_rn(__fdividef(acc, l)));
  asm volatile("st.shared.u16 [%0], %1;" ::"r"(dst_row + ((((lane >> 3) ^ ((row >> 1) & 3)) << 4) | ((lane & 7) << 1))), "h"(hv) : "memory");
}

constexpr int AT_STAGES = 4;
constexpr int NU = 12, UB = 16384;
struct FfnMaps { CUtensorMap o, wo, x, x1st, h2st, h2, wg, wu, hhst, hh, wd, x1, out, ost; };

__device__ __forceinline__ void release_units(uint32_t emptyb, int u, int n, int lane) {
  if (lane < 2 * n) {
    int e = u + (lane >> 1); if (e >= NU) e -= NU;
    asm volatile("{\n.reg .b32 ra;\nmapa.shared::cluster.u32 ra, %0, %1;\nmbarrier.arrive.shared::cluster.b64 _, [ra];\n}" ::"r"(emptyb + e * 8), "r"(lane & 1) : "memory");
  }
}
template <int NB> __device__ __forceinline__ void ffn_mainloop(float (&acc)[NB][64], int KT, uint32_t fullb, uint32_t emptyb, uint64_t da0, uint64_t db0,
                                                              int& u, uint32_t& pf, int lane) {
  constexpr int NUS = NB + 1;
  int up = 0;
#pragma unroll 1
  for (int k = 0; k < KT; k++) {
    mbar_wait(fullb + u * 8, (pf >> u) & 1);
    pf ^= 1u << u;
    const int ub = u + 1 == NU ? 0 : u + 1;
    const uint64_t da = da0 + u * (UB >> 4), db = db0 + ub * (UB >> 4);
    wg_fence();
#pragma unroll
    for (int kk = 0; kk < 4; kk++) {
#pragma unroll
      for (int b = 0; b < NB; b++) wgmma_ss_n128_tb1(acc[b], da + kk * 2, db + b * 1024 + kk * 128, (k | kk) != 0);
    }
    wg_commit();
    if (k > 0) { wg_wait<1>(); release_units(emptyb, up, NUS, lane); }
    up = u;
    u += NUS; if (u >= NU) u -= NU;
  }
  wg_wait<0>();
  release_units(emptyb, up, NUS, lane);
#pragma unroll
  for (int b = 0; b < NB; b++) fence_regs(acc[b]);
}
__device__ __forceinline__ int glu_tile(int q, int r) { return r < 2 ? q + 66 * r : 132 + (r - 2) * 34 + (q - 32); }

__global__ void __launch_bounds__(640, 1) k_af(const __grid_constant__ FfnMaps tm, const bf16* __restrict__ wo) {
  extern __shared__ uint8_t smem_raw[];
  __shared__ uint64_t abar[2 * AT_STAGES], qbar[2], obar[2], full[NU], empty[NU], resbar[2], stgfree[2], attdone, modbar, kdone;
  __shared__ __align__(16) uint32_t smod[320];
  constexpr int STAGES = AT_STAGES, NT = S_ / 128, UPC = 2;
  const uint32_t sbase = (smem_u32(smem_raw) + 1023) & ~1023u, stg = sbase + NU * UB;
  const uint32_t qs = sbase + 6 * UB, kb = sbase + 7 * UB, vb = sbase + 10 * UB;
  constexpr int QU = 3 * UB;
  const int wg = __shfl_sync(~0u, threadIdx.x / 128, 0), tid = threadIdx.x % 128, warp = __shfl_sync(~0u, tid / 32, 0), lane = tid % 32;
  const int q = blockIdx.x >> 1, rk = blockIdx.x & 1;
  const bool has_wo = q < 64, has_down = q < 32;
  const int nglu = q < 32 ? 2 : (q < 56 ? 5 : 4);
  const int mi0 = (q & 7) * 2 + rk, ni0 = q >> 3;
  if (threadIdx.x >= 32 && threadIdx.x < 46) prefetch_tmap(&tm.o + (threadIdx.x - 32));
  if (threadIdx.x == 0) {
    for (int s = 0; s < STAGES; s++) { mbar_init(smem_u32(&abar[s]), 1); mbar_init(smem_u32(&abar[STAGES + s]), 16); }
    for (int s = 0; s < NU; s++) { mbar_init(smem_u32(&full[s]), 1); mbar_init(smem_u32(&empty[s]), 16); }
    for (int s = 0; s < 2; s++) {
      mbar_init(smem_u32(&qbar[s]), 1); mbar_init(smem_u32(&obar[s]), 16);
      mbar_init(smem_u32(&resbar[s]), 1); mbar_init(smem_u32(&stgfree[s]), 1);
    }
    mbar_init(smem_u32(&attdone), 8);
    mbar_init(smem_u32(&modbar), 1);
    mbar_init(smem_u32(&kdone), 16);
    asm volatile("fence.mbarrier_init.release.cluster;" ::: "memory");
  }
  for (int i = threadIdx.x; i < STAGES * 512; i += 640)
    asm volatile("st.shared.v4.b32 [%0], {%1,%1,%1,%1};" ::"r"(stg + i * 16), "r"(0x3F803F80u) : "memory");
  fence_async();
  __syncthreads();
  cluster_arrive();
  if (wg == 4) {
    reg_dealloc<32>();
    const uint32_t fullb = smem_u32(full), emptyb = smem_u32(empty);
    if (warp == 0) {
      const uint32_t el = elect_one();
      if (has_wo) {
        int s = 0, ph = 1;
#pragma unroll 1
        for (int u = 0; u < UPC; u++) {
          const int h = u * 16 + (blockIdx.x >> 3);
          if (u == 1 && lane == 0) asm volatile("cp.async.bulk.prefetch.L2.global [%0], %1;" ::"l"(wo + (size_t)blockIdx.x * 8 * D_), "r"(8 * D_ * 2) : "memory");
#pragma unroll 1
          for (int j = 0; j < NT; j++) {
            const uint32_t fb = smem_u32(&abar[s]);
            mbar_wait_long(fb + STAGES * 8, ph);
            expect_tx_p(el, fb, 16384);
            if (u == 0 && j == 0) pdl_wait();
            bulk_ld_p(el, kb + s * 8192, g_qkv + ((size_t)(32 + h) * S_ + j * 128) * 32, 8192, fb);
            if (u == 0 && (j == 0 || j == 3)) {
              const int uq = j ? 1 : 0;
              expect_tx_p(el, smem_u32(&qbar[uq]), 16384);
              bulk_ld_p(el, qs + uq * QU, g_qkv + ((size_t)(uq * 16 + (blockIdx.x >> 3)) * S_ + (blockIdx.x & 7) * 256) * 32, 16384, smem_u32(&qbar[uq]));
            }
            bulk_ld_p(el, vb + s * 8192, g_qkv + ((size_t)(64 + h) * S_ + j * 128) * 32, 8192, fb);
            if (u == 0 && j == 0) { mbar_wait(fb, 0); }
            if (++s == STAGES) { s = 0; ph ^= 1; }
          }
        }
      }
      pdl_wait();
      cluster_wait();
      wait_count_slow(&g_cnt[C_MOD], 128);
      __syncwarp();
      int u = 0;
      uint32_t pe = has_wo ? 0x03Fu : 0xFFFu;
      auto acquire = [&](int n, uint32_t bytes) {
#pragma unroll
        for (int i = 0; i < n; i++) mbar_wait_long(emptyb + (u + i) * 8, (pe >> (u + i)) & 1);
        pe ^= ((1u << n) - 1) << u;
        expect_tx_p(el, fullb + u * 8, bytes);
      };
      auto nxt = [&](int v, int n) { v += n; return v >= NU ? v - NU : v; };
      if (has_wo) {
#pragma unroll 1
        for (int k = 0; k < 16; k++) {
          acquire(2, 2 * UB);
          tma2d_mc_p(el, sbase + (u + 1) * UB + rk * 8192, &tm.wo, ni0 * 128 + rk * 64, k * 64, fullb + u * 8);
          if ((k & 7) == 0) {
            wait_count(&g_cnt[C_O + (2 * k + mi0) * 32], 16);
            __syncwarp();
            fence_async();
          }
          tma2d_p(el, sbase + u * UB, &tm.o, k * 64, mi0 * 128, fullb + u * 8);
          u = nxt(u, 2);
        }
        u = 9;
      }
#pragma unroll 1
      for (int r = 0; r < nglu; r++) {
        const int t = glu_tile(q, r), mi = (t & 7) * 2 + rk, nj = t >> 3;
        int u0 = u;
        const int kd = __shfl_sync(~0u, ld_acquire(&g_cnt[C_H2 + mi * 32]), 0) >= 16 ? 0 : 3;
        if (kd == 0) fence_async();
#pragma unroll 1
        for (int k = 0; k < 16; k++) {
          acquire(3, 3 * UB);
          const uint32_t b = sbase + (u + 1) * UB + rk * 8192, fb = fullb + u * 8;
          tma2d_mc_p(el, b, &tm.wg, nj * 128 + rk * 64, k * 64, fb);
          tma2d_mc_p(el, b + 16384, &tm.wu, nj * 128 + rk * 64, k * 64, fb);
          if (k == 3 && kd) {
            wait_count(&g_cnt[C_H2 + mi * 32], 16);
            __syncwarp();
            fence_async();
#pragma unroll 1
            for (int i = 0; i < 3; i++) { tma2d_p(el, sbase + u0 * UB, &tm.h2, i * 64, mi * 128, fullb + u0 * 8); u0 = nxt(u0, 3); }
          }
          if (k >= kd) tma2d_p(el, sbase + u * UB, &tm.h2, k * 64, mi * 128, fb);
          u = nxt(u, 3);
        }
      }
      if (has_down) {
        uint32_t ready = 0;
#pragma unroll 1
        for (int k = 0; k < 56; k++) {
          acquire(3, 3 * UB);
          const uint32_t b = sbase + (u + 1) * UB + rk * 16384, fb = fullb + u * 8;
          tma2d_mc_p(el, b, &tm.wd, ni0 * 256 + rk * 128, k * 64, fb);
          tma2d_mc_p(el, b + 8192, &tm.wd, ni0 * 256 + rk * 128 + 64, k * 64, fb);
          if (!((ready >> (k >> 1)) & 1)) {
            for (unsigned n = 0; !((ready >> (k >> 1)) & 1); n++) {
              ready = __ballot_sync(~0u, lane < 28 && ld_acquire(&g_cnt[C_HH + mi0 * 32 + lane]) >= 2);
              if (n > (1u << 22)) __trap();
            }
            fence_async();
          }
          tma2d_p(el, sbase + u * UB, &tm.hh, k * 64, mi0 * 128, fb);
          u = nxt(u, 3);
        }
#pragma unroll 1
        for (int i = 0; i < 2; i++) {
          acquire(3, 2 * UB);
          tma2d_p(el, sbase + u * UB, &tm.x1, ni0 * 256 + i * 128, mi0 * 128, fullb + u * 8);
          tma2d_p(el, sbase + (u + 1) * UB, &tm.x1, ni0 * 256 + i * 128 + 64, mi0 * 128, fullb + u * 8);
          u = nxt(u, 3);
        }
      }
    } else if (warp < 3) {
      cluster_wait();
      if (has_wo && warp == 1) {
        pdl_wait();
        const int i = blockIdx.x * 48 + lane;
#pragma unroll
        for (int k = 0; k < 2; k++) {
          const int col = i + k * 32;
          if (k == 0 || lane < 16) {
            float v = bf_round(__ldcg(g_acc + col));
            if ((col >> 10) == 4) v = bf_round(1.f + v);
            g_modh[col] = __float2bfloat16_rn(v);
            g_acc[col] = 0.f;
          }
        }
        mbar_wait_long(smem_u32(&obar[0]), 0);
        if (blockIdx.x < 41) g_cnt[blockIdx.x * 32 + lane] = 0;
        uint4* st = (uint4*)g_stat + blockIdx.x * 64;
        st[lane] = st[32 + lane] = make_uint4(~0u, ~0u, ~0u, ~0u);
        __syncwarp();
        if (lane == 0) red_release(&g_cnt[C_MOD], 1);
      }
      if (has_wo && warp == 2) {
#pragma unroll 1
        for (int u = 0; u < UPC; u++) {
          if (lane == 0) {
            mbar_wait_long(smem_u32(&obar[u]), 0);
            tma2d_store(&tm.ost, (u * 16 + (blockIdx.x >> 3)) * 32, (blockIdx.x & 7) * 256, qs + u * QU);
            asm volatile("cp.async.bulk.commit_group;" ::: "memory");
            asm volatile("cp.async.bulk.wait_group.read 0;" ::: "memory");
          }
          __syncwarp();
          if (lane < 2) arrive8_remote(emptyb + (6 + 3 * u) * 8, lane);
          if (lane == 0) {
            asm volatile("cp.async.bulk.wait_group 0;" ::: "memory");
            red_relaxed(&g_cnt[C_O + (u * 16 + (blockIdx.x & 7) * 2) * 32], 1);
            red_relaxed(&g_cnt[C_O + (u * 16 + (blockIdx.x & 7) * 2 + 1) * 32], 1);
          }
          __syncwarp();
        }
      }
      const int w = warp - 1;
      const uint32_t sw = stg + w * 8192, rb = smem_u32(&resbar[w]), sf = smem_u32(&stgfree[w]);
      auto store2 = [&](const CUtensorMap* m, uint32_t src, int col, int row) {
        tma2d_store(m, col, row, src); tma2d_store(m, col + 64, row, src + 16384);
      };
      auto commit_read = [&]() {
        asm volatile("cp.async.bulk.commit_group;" ::: "memory");
        asm volatile("cp.async.bulk.wait_group.read 0;" ::: "memory");
      };
      if (has_wo) {
        mbar_wait_long(smem_u32(&attdone), 0);
        if (lane == 0) { mbar_expect_tx(rb, 16384); tma2d(sw, &tm.x, ni0 * 128, mi0 * 128 + w * 64, rb); tma2d(sw + 16384, &tm.x, ni0 * 128 + 64, mi0 * 128 + w * 64, rb); }
        named_bar(4 + w, 160);
        if (lane == 0) { store2(&tm.x1st, sw, ni0 * 128, mi0 * 128 + w * 64); commit_read(); mbar_arrive(sf); }
        __syncwarp();
        named_bar(4 + w, 160);
        if (lane == 0) {
          store2(&tm.h2st, sw, ni0 * 128, mi0 * 128 + w * 64); commit_read(); mbar_arrive(sf);
          asm volatile("cp.async.bulk.wait_group 0;" ::: "memory");
          red_relaxed(&g_cnt[C_H2 + mi0 * 32], 1);
        }
        __syncwarp();
      }
      for (int r = 0; r < nglu; r++) {
        const int t = glu_tile(q, r), mi = (t & 7) * 2 + rk, nj = t >> 3;
        named_bar(4 + w, 160);
        if (lane == 0) {
          store2(&tm.hhst, sw, nj * 128, mi * 128 + w * 64); commit_read(); mbar_arrive(sf);
          asm volatile("cp.async.bulk.wait_group 0;" ::: "memory");
          red_relaxed(&g_cnt[C_HH + mi * 32 + nj], 1);
        }
        __syncwarp();
      }
      if (has_down) {
        for (int i = 0; i < 2; i++) {
          named_bar(4 + 2 * i + w, 160);
          if (lane == 0) { store2(&tm.out, sbase + (i ? 0 : 9) * UB + w * 8192, ni0 * 256 + i * 128, mi0 * 128 + w * 64); asm volatile("cp.async.bulk.commit_group;" ::: "memory"); }
          __syncwarp();
        }
        if (lane == 0) { asm volatile("cp.async.bulk.wait_group.read 0;" ::: "memory"); }
      }
    } else {
      cluster_wait();
      if (has_wo) {
        mbar_wait_long(smem_u32(&obar[0]), 0);
        wait_count_slow(&g_cnt[C_MOD], 128);
        if (lane < 16) {
#pragma unroll
          for (int v = 0; v < 3; v++) *(uint4*)(smod + v * 64 + lane * 4) = __ldcg((const uint4*)(g_modh + (2 + v) * D_ + ni0 * 128) + lane);
        }
        if (has_down) *(uint4*)(smod + 192 + lane * 4) = __ldcg((const uint4*)(g_modh + 5 * D_ + ni0 * 256) + lane);
        __syncwarp();
        if (lane == 0) mbar_arrive(smem_u32(&modbar));
        mbar_wait_long(smem_u32(&kdone), 0);
        if (lane < 2) arrive8_remote(emptyb + 7 * 8, lane);
      }
    }
  } else {
    reg_alloc<112>();
    cluster_wait();
    if (has_wo) {
      static_assert(STAGES == 4, "");
      uint32_t ph = 0, so = 0;
      const uint32_t fullb = __shfl_sync(~0u, smem_u32(abar), 0), emptyb = fullb + STAGES * 8, l0 = elect_one();
      const uint64_t dk0 = 0x8000002000000000ull | __shfl_sync(~0u, (uint32_t)make_desc(kb, 16, 512, 2), 0);
      const uint64_t dv0 = 0x8000002000000000ull | __shfl_sync(~0u, (uint32_t)make_desc(vb, STAGES * 8192, 512, 2), 0);
      const int qrow = wg * 64 + warp * 16 + (lane & 15);
      const uint32_t qa = qs + qrow * 64 + (((lane >> 4) ^ ((qrow >> 1) & 3)) << 4);
      uint32_t qf[8], p[16];
      float o[20], sc[32], B0, B1, M0, M1;
      uint32_t badrows = 0;
      uint32_t c_one, c_s;
      asm volatile("ld.shared.b32 %0, [%1];" : "=r"(c_one) : "r"(stg));
      c_s = c_one - (0x3F803F80u - 0x3EF63EF6u);
      auto load_q = [&](int u) {
        mbar_wait(smem_u32(&qbar[u]), 0);
        uint32_t r[4];
        ldsm4(r, qa + u * QU); qf[0] = r[0]; qf[1] = r[1]; qf[2] = r[2]; qf[3] = r[3];
        ldsm4(r, (qa ^ 32) + u * QU); qf[4] = r[0]; qf[5] = r[1]; qf[6] = r[2]; qf[7] = r[3];
      };
      auto set_shift = [&]() {
        M0 = sc[0]; M1 = sc[2];
#pragma unroll
        for (int i = 0; i < 8; i++) { M0 = fmaxf(M0, fmaxf(sc[4 * i], sc[4 * i + 1])); M1 = fmaxf(M1, fmaxf(sc[4 * i + 2], sc[4 * i + 3])); }
        M0 = fmaxf(M0, __shfl_xor_sync(~0u, M0, 1)); M0 = fmaxf(M0, __shfl_xor_sync(~0u, M0, 2));
        M1 = fmaxf(M1, __shfl_xor_sync(~0u, M1, 1)); M1 = fmaxf(M1, __shfl_xor_sync(~0u, M1, 2));
        M0 = rintf(fmaf(M0, SCQ, OFFS)); M1 = rintf(fmaf(M1, SCQ, OFFS));
        if (!(fabsf(M0) < 30000.f)) M0 = __int_as_float(0x7fffffff);
        if (!(fabsf(M1) < 30000.f)) M1 = __int_as_float(0x7fffffff);
        B0 = M0 == M0 ? den_bits(M0) : M0; B1 = M1 == M1 ? den_bits(M1) : M1;
      };
      auto pv = [&](uint64_t dv) {
#pragma unroll
        for (int kk = 0; kk < 4; kk++) wgmma_rs_n40_tb1(o, p[4 * kk], p[4 * kk + 1], p[4 * kk + 2], p[4 * kk + 3], dv + kk * 64, 1);
        wg_commit();
      };
      load_q(0);
      mbar_wait(fullb, 0);
      wg_fence(); qk64(sc, qf, dk0); wg_commit(); wg_wait<0>(); fence_regs(sc);
      set_shift();
      exp_a(sc, B0, B1, M0, M1); exp_b(sc, p, c_one, c_s);
#pragma unroll 1
      for (int u = 0; u < UPC; u++) {
#pragma unroll
        for (int i = 0; i < 20; i++) o[i] = 0.f;
        auto step = [&](uint64_t dk, uint64_t dv) {
          wg_fence();
          qk64(sc, qf, dk);
          wg_commit();
          pv(dv);
          wg_wait<1>(); fence_regs(sc);
          exp_a(sc, B0, B1, M0, M1);
          wg_wait<0>();
        };
#pragma unroll 1
        for (int j = 0; j < NT - 1; j++) {
          const uint32_t sn = (so + 512) & 0x600;
          if (sn == 0) ph ^= 1;
          step(dk0 + so + 256, dv0 + so);
          exp_b(sc, p, c_one, c_s);
          mbar_wait_nb(fullb + (sn >> 6), ph);
          step(dk0 + sn, dv0 + so + 256);
          arrive_p(l0, emptyb + (so >> 6));
          exp_b(sc, p, c_one, c_s);
          so = sn;
        }
        {
          if (u == 1 && lane == 0) mbar_arrive(smem_u32(&kdone));
          step(dk0 + 3 * 512 + 256, dv0 + 3 * 512);
          exp_b(sc, p, c_one, c_s);
          load_q(1);
          ph ^= 1;
          if (u == 0) mbar_wait_nb(fullb, ph);
          wg_fence();
          qk64(sc, qf, dk0 + u * 3 * 512);
          wg_commit();
          pv(dv0 + 3 * 512 + 256);
          wg_wait<1>(); fence_regs(sc);
          set_shift();
          wg_wait<0>();
          arrive_p(l0, emptyb + 3 * 8);
          if (u == 0) { exp_a(sc, B0, B1, M0, M1); exp_b(sc, p, c_one, c_s); }
          so = 0;
        }
        fence_regs(o);
        const float r0 = __fdividef(1.f, o[16]), r1 = __fdividef(1.f, o[18]);
        float a0 = 0.f, a1 = 0.f;
#pragma unroll
        for (int i = 0; i < 4; i++) { a0 += fabsf(o[4 * i]) + fabsf(o[4 * i + 1]); a1 += fabsf(o[4 * i + 2]) + fabsf(o[4 * i + 3]); }
        const bool bad0 = !(o[16] > 0.f && o[16] < 1e36f && a0 < 1e37f), bad1 = !(o[18] > 0.f && o[18] < 1e36f && a1 < 1e37f);
        stsm4(qa + u * QU, pack_bf16(o[0] * r0, o[1] * r0), pack_bf16(o[2] * r1, o[3] * r1), pack_bf16(o[4] * r0, o[5] * r0), pack_bf16(o[6] * r1, o[7] * r1));
        stsm4((qa ^ 32) + u * QU, pack_bf16(o[8] * r0, o[9] * r0), pack_bf16(o[10] * r1, o[11] * r1), pack_bf16(o[12] * r0, o[13] * r0), pack_bf16(o[14] * r1, o[15] * r1));
        uint32_t m = 0;
        {
          const uint32_t m0 = __ballot_sync(~0u, bad0), m1 = __ballot_sync(~0u, bad1);
          if (m0 | m1) m = __ballot_sync(~0u, lane < 16 && (((lane < 8 ? m0 : m1) >> (4 * (lane & 7))) & 15));
        }
        badrows |= m << (16 * u);
        if (m == 0) {
          fence_async();
          __syncwarp();
          if (lane == 0) mbar_arrive(smem_u32(&obar[u]));
        }
      }
      if (badrows) {
#pragma unroll 1
        for (int r = 0; r < 32; r++) {
          const int u = r >> 4, lr = wg * 64 + warp * 16 + (r & 15);
          if ((badrows >> r) & 1) attn_row_exact(u * 16 + (blockIdx.x >> 3), (blockIdx.x & 7) * 256 + lr, lane, qs + u * QU + lr * 64);
          if ((r & 15) == 15 && ((badrows >> (r & 16)) & 0xFFFF)) {
            fence_async();
            __syncwarp();
            if (lane == 0) mbar_arrive(smem_u32(&obar[u]));
          }
        }
      }

      named_bar(12, 512);
    }
    if (wg >= 2) {
      reg_dealloc<24>();
    } else {
      reg_alloc<200>();
      const uint32_t fullb = smem_u32(full), emptyb = smem_u32(empty);
      if (has_wo) {
        release_units(emptyb, 8, 1, lane);
        release_units(emptyb, 10, 2, lane);
        if (lane == 0) mbar_arrive(smem_u32(&attdone));
      }
      const int w = wg, g = lane >> 2, t4 = lane & 3;
      int u = 0;
      uint32_t pf = 0, psf = 0;
      const uint64_t da0 = make_desc(sbase + w * 8192, 16, 1024, 1), db0 = make_desc(sbase, 8192, 1024, 1);
      const int srow = warp * 16 + (lane & 7) + ((lane >> 3) & 1) * 8;
      const uint32_t soff = w * 8192 + srow * 128;
      const uint32_t sf = smem_u32(&stgfree[w]), rb = smem_u32(&resbar[w]);
      auto sa = [&](uint32_t base, int j) { const int ch = 2 * j + (lane >> 4); return base + soff + (ch >> 3) * 16384 + (((ch & 7) ^ (srow & 7)) << 4); };
      if (has_wo) {
        float accw[1][64];
        float (&acc)[64] = accw[0];
        ffn_mainloop<1>(accw, 16, fullb, emptyb, da0, db0, u, pf, lane);
        u = 9;
        mbar_wait(rb, 0);
        mbar_wait(smem_u32(&modbar), 0);
        float s0 = 0.f, s1 = 0.f;
#pragma unroll
        for (int j = 0; j < 8; j++) {
          uint32_t r[4];
          ldsm4(r, sa(stg, j));
#pragma unroll
          for (int e = 0; e < 4; e++) {
            const uint32_t gg = smod[(2 * j + (e >> 1)) * 4 + t4];
            acc[8 * j + 2 * e] = fmaf(bf_lo(gg), acc[8 * j + 2 * e], bf_lo(r[e])); acc[8 * j + 2 * e + 1] = fmaf(bf_hi(gg), acc[8 * j + 2 * e + 1], bf_hi(r[e]));
            if (e & 1) s1 += acc[8 * j + 2 * e] + acc[8 * j + 2 * e + 1]; else s0 += acc[8 * j + 2 * e] + acc[8 * j + 2 * e + 1];
          }
        }
        s0 += __shfl_xor_sync(~0u, s0, 1); s0 += __shfl_xor_sync(~0u, s0, 2);
        s1 += __shfl_xor_sync(~0u, s1, 1); s1 += __shfl_xor_sync(~0u, s1, 2);
        float q0 = 0.f, q1 = 0.f;
        {
          const float m0 = s0 * (1.f / 128), m1 = s1 * (1.f / 128);
#pragma unroll
          for (int i = 0; i < 16; i++) {
            const float a = acc[4 * i] - m0, b = acc[4 * i + 1] - m0, cc = acc[4 * i + 2] - m1, d = acc[4 * i + 3] - m1;
            q0 = fmaf(a, a, fmaf(b, b, q0)); q1 = fmaf(cc, cc, fmaf(d, d, q1));
          }
        }
        q0 += __shfl_xor_sync(~0u, q0, 1); q0 += __shfl_xor_sync(~0u, q0, 2);
        q1 += __shfl_xor_sync(~0u, q1, 1); q1 += __shfl_xor_sync(~0u, q1, 2);
        const int grow = mi0 * 128 + w * 64 + warp * 16 + g;
        if (t4 < 2) {
          uint32_t a = __float_as_uint(t4 ? s1 : s0);
          if (a == 0xFFFFFFFFu) a = 0x7FFFFFFFu;
          const unsigned long long pk = (unsigned long long)a | ((unsigned long long)__float_as_uint(t4 ? q1 : q0) << 32);
          asm volatile("red.relaxed.gpu.global.and.b64 [%0], %1;" ::"l"(g_stat + (grow + 8 * t4) * 8 + ni0), "l"(pk) : "memory");
        }
#pragma unroll
        for (int j = 0; j < 8; j++)
          stsm4(sa(stg, j), pack_bf16(acc[8 * j], acc[8 * j + 1]), pack_bf16(acc[8 * j + 2], acc[8 * j + 3]), pack_bf16(acc[8 * j + 4], acc[8 * j + 5]), pack_bf16(acc[8 * j + 6], acc[8 * j + 7]));
        fence_async();
        bar_arrive(4 + w, 160);
        float mean[2], rstd[2];
        {
          unsigned long long p[2][2];
          auto ldst = [&](unsigned long long (&v)[2][2]) {
#pragma unroll
            for (int r = 0; r < 2; r++)
              asm volatile("ld.relaxed.gpu.global.v2.b64 {%0,%1}, [%2];" : "=l"(v[r][0]), "=l"(v[r][1]) : "l"(g_stat + (grow + 8 * r) * 8 + t4 * 2) : "memory");
          };
          auto okst = [&](unsigned long long (&v)[2][2]) {
            return __all_sync(~0u, (uint32_t)v[0][0] != ~0u && (uint32_t)v[0][1] != ~0u && (uint32_t)v[1][0] != ~0u && (uint32_t)v[1][1] != ~0u);
          };
          for (unsigned n = 0;; n++) {
            ldst(p);
            if (okst(p)) break;
            if (n > (1u << 22)) __trap();
          }
#pragma unroll
          for (int r = 0; r < 2; r++) {
            const float sa0 = __uint_as_float((uint32_t)p[r][0]), qa0 = __uint_as_float((uint32_t)(p[r][0] >> 32));
            const float sa1 = __uint_as_float((uint32_t)p[r][1]), qa1 = __uint_as_float((uint32_t)(p[r][1] >> 32));
            float s = sa0 + sa1;
            s += __shfl_xor_sync(~0u, s, 1); s += __shfl_xor_sync(~0u, s, 2);
            mean[r] = s * (1.f / D_);
            const float d0 = sa0 * (1.f / 128) - mean[r], d1 = sa1 * (1.f / 128) - mean[r];
            float qq = qa0 + qa1 + 128.f * (d0 * d0 + d1 * d1);
            qq += __shfl_xor_sync(~0u, qq, 1); qq += __shfl_xor_sync(~0u, qq, 2);
            rstd[r] = rsqrtf(qq * (1.f / D_) + 1e-5f);
          }
        }
        mbar_wait(sf, psf); psf ^= 1;
#pragma unroll
        for (int j = 0; j < 8; j++) {
          uint32_t o[4];
#pragma unroll
          for (int e = 0; e < 4; e++) {
            const uint32_t a = smod[128 + (2 * j + (e >> 1)) * 4 + t4], b = smod[64 + (2 * j + (e >> 1)) * 4 + t4];
            o[e] = pack_bf16(fmaf((acc[8 * j + 2 * e] - mean[e & 1]) * rstd[e & 1], bf_lo(a), bf_lo(b)), fmaf((acc[8 * j + 2 * e + 1] - mean[e & 1]) * rstd[e & 1], bf_hi(a), bf_hi(b)));
          }
          stsm4(sa(stg, j), o[0], o[1], o[2], o[3]);
        }
        fence_async();
        bar_arrive(4 + w, 160);
      }
      for (int r = 0; r < nglu; r++) {
        float acc[2][64];
        ffn_mainloop<2>(acc, 16, fullb, emptyb, da0, db0, u, pf, lane);
        if (has_wo || r > 0) { mbar_wait(sf, psf); psf ^= 1; }
#pragma unroll
        for (int j = 0; j < 8; j++)
          stsm4(sa(stg, j), pack_bf16(acc[0][8 * j] * acc[1][8 * j], acc[0][8 * j + 1] * acc[1][8 * j + 1]), pack_bf16(acc[0][8 * j + 2] * acc[1][8 * j + 2], acc[0][8 * j + 3] * acc[1][8 * j + 3]),
                pack_bf16(acc[0][8 * j + 4] * acc[1][8 * j + 4], acc[0][8 * j + 5] * acc[1][8 * j + 5]), pack_bf16(acc[0][8 * j + 6] * acc[1][8 * j + 6], acc[0][8 * j + 7] * acc[1][8 * j + 7]));
        fence_async();
        bar_arrive(4 + w, 160);
      }
      if (has_down) {
        uint32_t gt[32];
#pragma unroll
        for (int i = 0; i < 32; i++) gt[i] = smod[192 + i * 4 + t4];
        float acc[2][64];
        ffn_mainloop<2>(acc, 56, fullb, emptyb, da0, db0, u, pf, lane);
#pragma unroll
        for (int i = 0; i < 2; i++) {
          const int ur = i ? 0 : 9;
          mbar_wait(fullb + ur * 8, (pf >> ur) & 1);
#pragma unroll
          for (int j = 0; j < 8; j++) {
            uint32_t r[4], o[4];
            ldsm4(r, sa(sbase + ur * UB, j));
#pragma unroll
            for (int e = 0; e < 4; e++) {
              const uint32_t gg = gt[16 * i + 2 * j + (e >> 1)];
              o[e] = pack_bf16(fmaf(bf_lo(gg), acc[i][8 * j + 2 * e], bf_lo(r[e])), fmaf(bf_hi(gg), acc[i][8 * j + 2 * e + 1], bf_hi(r[e])));
            }
            stsm4(sa(sbase + ur * UB, j), o[0], o[1], o[2], o[3]);
          }
          fence_async();
          if (i == 0) bar_arrive(4 + w, 160); else bar_arrive(6 + w, 160);
        }
      }

    }
  }
  asm volatile("barrier.cluster.arrive.relaxed.aligned;\nbarrier.cluster.wait.aligned;" ::: "memory");
}

typedef CUresult (*EncFn)(CUtensorMap*, CUtensorMapDataType, cuuint32_t, void*, const cuuint64_t*, const cuuint64_t*, const cuuint32_t*, const cuuint32_t*,
                          CUtensorMapInterleave, CUtensorMapSwizzle, CUtensorMapL2promotion, CUtensorMapFloatOOBfill);
static CUtensorMap mk_map(EncFn enc, const void* p, uint64_t cols, uint64_t rows, uint32_t bc, uint32_t br, CUtensorMapSwizzle sw) {
  CUtensorMap tm;
  cuuint64_t gd[2] = {cols, rows}, gs[1] = {cols * 2};
  cuuint32_t bd[2] = {bc, br}, es[2] = {1, 1};
  enc(&tm, CU_TENSOR_MAP_DATA_TYPE_BFLOAT16, 2, (void*)p, gd, gs, bd, es, CU_TENSOR_MAP_INTERLEAVE_NONE, sw, CU_TENSOR_MAP_L2_PROMOTION_L2_256B, CU_TENSOR_MAP_FLOAT_OOB_FILL_NONE);
  return tm;
}
template <typename... KArgs, typename... Args>
static void launch(void (*k)(KArgs...), int grid, int block, int smem, bool pdl, int cluster, Args... args) {
  cudaLaunchConfig_t cfg = {};
  cfg.gridDim = dim3(grid); cfg.blockDim = dim3(block); cfg.dynamicSmemBytes = smem; cfg.stream = cudaStreamPerThread;
  cudaLaunchAttribute at[2];
  int n = 0;
  if (pdl) { at[n].id = cudaLaunchAttributeProgrammaticStreamSerialization; at[n].val.programmaticStreamSerializationAllowed = 1; n++; }
  if (cluster > 1) { at[n].id = cudaLaunchAttributeClusterDimension; at[n].val.clusterDim.x = cluster; at[n].val.clusterDim.y = 1; at[n].val.clusterDim.z = 1; n++; }
  cfg.attrs = at; cfg.numAttrs = n;
  cudaLaunchKernelEx(&cfg, k, KArgs(args)...);
}

extern "C" void kernel_launch(void* const* d_in, const int* in_sizes, int n_in, void* d_out, int out_size) {
  const bf16 *x = (const bf16*)d_in[0], *wqkv = (const bf16*)d_in[1], *wo = (const bf16*)d_in[2];
  const bf16 *wg = (const bf16*)d_in[4], *wu = (const bf16*)d_in[5], *wd = (const bf16*)d_in[6], *c = (const bf16*)d_in[7], *wmod = (const bf16*)d_in[8];
  static bool init = false;
  static const void* cached[10];
  static CUtensorMap mH, mWqkv;
  static FfnMaps fm;
  constexpr int SM_QKV = 4 * (256 + 192) * 128 + 1024, SM_FFN = NU * UB + 32768 + 1024;
  bool same = init;
  for (int i = 0; i < 9 && same; i++) same = cached[i] == d_in[i];
  same = same && cached[9] == d_out;
  if (!same) {
    void* fn = nullptr; cudaDriverEntryPointQueryResult qr;
    cudaGetDriverEntryPoint("cuTensorMapEncodeTiled", &fn, cudaEnableDefault, &qr);
    EncFn enc = (EncFn)fn;
    void *ph, *po, *px1, *ph2, *phh;
    cudaGetSymbolAddress(&ph, g_h); cudaGetSymbolAddress(&po, g_o);
    cudaGetSymbolAddress(&px1, g_x1); cudaGetSymbolAddress(&ph2, g_h2); cudaGetSymbolAddress(&phh, g_hh);
    const CUtensorMapSwizzle S128 = CU_TENSOR_MAP_SWIZZLE_128B;
    mH = mk_map(enc, ph, D_, S_, 64, 128, S128);      mWqkv = mk_map(enc, wqkv, 3 * D_, D_, 64, 64, S128);
    fm.ost = mk_map(enc, po, D_, S_, 32, 256, CU_TENSOR_MAP_SWIZZLE_64B);
    fm.o = mk_map(enc, po, D_, S_, 64, 128, S128);     fm.wo = mk_map(enc, wo, D_, D_, 64, 64, S128);
    fm.x = mk_map(enc, x, D_, S_, 64, 64, S128);       fm.x1st = mk_map(enc, px1, D_, S_, 64, 64, S128);
    fm.h2st = mk_map(enc, ph2, D_, S_, 64, 64, S128);  fm.h2 = mk_map(enc, ph2, D_, S_, 64, 128, S128);
    fm.wg = mk_map(enc, wg, F_, D_, 64, 64, S128);     fm.wu = mk_map(enc, wu, F_, D_, 64, 64, S128);
    fm.hhst = mk_map(enc, phh, F_, S_, 64, 64, S128);  fm.hh = mk_map(enc, phh, F_, S_, 64, 128, S128);
    fm.wd = mk_map(enc, wd, D_, F_, 64, 64, S128);     fm.x1 = mk_map(enc, px1, D_, S_, 64, 128, S128);
    fm.out = mk_map(enc, d_out, D_, S_, 64, 64, S128);
    cudaFuncSetAttribute(k_qkv, cudaFuncAttributeMaxDynamicSharedMemorySize, SM_QKV);
    cudaFuncSetAttribute(k_af, cudaFuncAttributeMaxDynamicSharedMemorySize, SM_FFN);
    for (int i = 0; i < 9; i++) cached[i] = d_in[i];
    cached[9] = d_out;
    init = true;
  }
  launch(k_qkv, 128, 384, SM_QKV, false, 2, mH, mWqkv, x, c, wmod);
  launch(k_af, 132, 640, SM_FFN, true, 2, fm, wo);
}
```
